```python
import torch

def _softmax(x, axis=-1):
    return torch.softmax(x, dim=axis)
def _gelu(x):
    return torch.nn.functional.gelu(x, approximate="tanh")
def _silu(x):
    return torch.nn.functional.silu(x)
def _sigmoid(x):
    return torch.sigmoid(x)
def _layernorm(x, axis=-1, eps=1e-5):
    m = x.mean(dim=axis, keepdim=True)
    v = x.var(dim=axis, keepdim=True, unbiased=False)
    return (x - m) / torch.sqrt(v + eps)
def _scatter_add(tgt, idx, src, axis=0):
    return tgt.clone().index_add_(axis, idx, src)
def _segment_sum(src, seg, n):
    out = torch.zeros((n,) + src.shape[1:], dtype=src.dtype)
    return out.index_add_(0, seg, src)
def _pad(x, pw):
    flat = tuple(v for pair in reversed(pw) for v in pair)
    return torch.nn.functional.pad(x, flat)

kernel_name = 'standalone__deepnorm__sampling'

def setup_inputs():

    _w = (lambda a: (lambda t: t.to(torch.bfloat16) if t.is_floating_point() else t)(torch.as_tensor(a)))
    B, S, D = 1024, 4, 1024
    return {
        "x": _w((lambda *s: torch.randn(*s, dtype=torch.bfloat16) * 0.05)(B, S, D)),
        "f": _w((lambda *s: torch.randn(*s, dtype=torch.bfloat16) * 0.05)(B, S, D)),
        "g": _w((lambda *s: torch.randn(*s, dtype=torch.bfloat16) * 0.05)(D) + 1.0),
        "b": _w((lambda *s: torch.randn(*s, dtype=torch.bfloat16) * 0.4)(D)),
        "alpha": _w(float(2.0)),
    }

def reference(x, f, g, b, alpha):
    return _layernorm(alpha * x + f, axis=-1) * g + b
```

```cpp
#include <cuda_runtime.h>
#include <cuda_bf16.h>
#include <stdint.h>

namespace {

constexpr int D = 1024;
constexpr int ROW_BYTES = D * 2;
constexpr int NCTA = 132;
constexpr int NW = 8;
constexpr int WIN = 8;
constexpr int MAXROWS = 32;

__device__ __forceinline__ uint32_t smem_u32(const void* p) { return (uint32_t)__cvta_generic_to_shared(p); }
__device__ __forceinline__ uint4 ldg_nc(const void* p) {
    uint4 v; asm volatile("ld.global.nc.v4.u32 {%0,%1,%2,%3}, [%4];" : "=r"(v.x), "=r"(v.y), "=r"(v.z), "=r"(v.w) : "l"(p)); return v;
}
__device__ __forceinline__ void stg(void* p, uint4 v) {
    asm volatile("st.global.v4.u32 [%4], {%0,%1,%2,%3};" :: "r"(v.x), "r"(v.y), "r"(v.z), "r"(v.w), "l"(p) : "memory");
}
__device__ __forceinline__ uint4 lds128(uint32_t a) {
    uint4 v; asm volatile("ld.shared.v4.u32 {%0,%1,%2,%3}, [%4];" : "=r"(v.x), "=r"(v.y), "=r"(v.z), "=r"(v.w) : "r"(a)); return v;
}
__device__ __forceinline__ void mbar_expect_tx(uint32_t bar, uint32_t bytes) {
    asm volatile("mbarrier.arrive.expect_tx.shared::cta.b64 _, [%0], %1;" :: "r"(bar), "r"(bytes) : "memory");
}
__device__ __forceinline__ void mbar_wait(uint32_t bar, uint32_t parity) {
    asm volatile("{\n.reg .pred p;\nWAIT_LOOP:\nmbarrier.try_wait.parity.shared::cta.b64 p, [%0], %1;\n@p bra WAIT_DONE;\nbra WAIT_LOOP;\nWAIT_DONE:\n}" :: "r"(bar), "r"(parity) : "memory");
}
__device__ __forceinline__ void bulk_g2s(uint32_t dst, const void* src, uint32_t bytes, uint32_t bar) {
    asm volatile("cp.async.bulk.shared::cluster.global.mbarrier::complete_tx::bytes [%0], [%1], %2, [%3];" :: "r"(dst), "l"(src), "r"(bytes), "r"(bar) : "memory");
}
__device__ __forceinline__ uint32_t bf2_fma(uint32_t a, uint32_t b, uint32_t c) {
    uint32_t d; asm("fma.rn.bf16x2 %0, %1, %2, %3;" : "=r"(d) : "r"(a), "r"(b), "r"(c)); return d;
}
__device__ __forceinline__ float bf_lo(uint32_t v) { return __uint_as_float(v << 16); }
__device__ __forceinline__ float bf_hi(uint32_t v) { return __uint_as_float(v & 0xffff0000u); }
__device__ __forceinline__ uint32_t pack_bf2(float lo, float hi) {
    uint32_t d; asm("cvt.rn.bf16x2.f32 %0, %1, %2;" : "=r"(d) : "f"(hi), "f"(lo)); return d;
}

__device__ __forceinline__ void row_math(const uint4 (&xv)[4], const uint4 (&fv)[4], const uint4 (&gv)[4], const uint4 (&bv)[4],
                                         uint32_t alpha2, uint4 (&o)[4]) {
    uint32_t y[16];
#pragma unroll
    for (int j = 0; j < 4; j++) {
        y[j * 4 + 0] = bf2_fma(alpha2, xv[j].x, fv[j].x);
        y[j * 4 + 1] = bf2_fma(alpha2, xv[j].y, fv[j].y);
        y[j * 4 + 2] = bf2_fma(alpha2, xv[j].z, fv[j].z);
        y[j * 4 + 3] = bf2_fma(alpha2, xv[j].w, fv[j].w);
    }
    float K = __shfl_sync(0xffffffffu, bf_lo(y[0]), 0);
    float d[32];
    float s0 = 0.f, s1 = 0.f, q0 = 0.f, q1 = 0.f;
#pragma unroll
    for (int i = 0; i < 16; i++) {
        float a = bf_lo(y[i]) - K, c = bf_hi(y[i]) - K;
        d[2 * i] = a; d[2 * i + 1] = c;
        s0 += a; s1 += c;
        q0 = fmaf(a, a, q0); q1 = fmaf(c, c, q1);
    }
    float s = s0 + s1, q = q0 + q1;
#pragma unroll
    for (int m = 16; m >= 1; m >>= 1) {
        s += __shfl_xor_sync(0xffffffffu, s, m);
        q += __shfl_xor_sync(0xffffffffu, q, m);
    }
    float mean = s * (1.0f / 1024.0f);
    float var = fmaxf(fmaf(-mean, mean, q * (1.0f / 1024.0f)), 0.f);
    float rstd = rsqrtf(var + 1e-5f);
    float nb = -mean * rstd;
    uint32_t r[16];
#pragma unroll
    for (int i = 0; i < 16; i++) r[i] = pack_bf2(fmaf(d[2 * i], rstd, nb), fmaf(d[2 * i + 1], rstd, nb));
#pragma unroll
    for (int j = 0; j < 4; j++) {
        o[j].x = bf2_fma(r[j * 4 + 0], gv[j].x, bv[j].x);
        o[j].y = bf2_fma(r[j * 4 + 1], gv[j].y, bv[j].y);
        o[j].z = bf2_fma(r[j * 4 + 2], gv[j].z, bv[j].z);
        o[j].w = bf2_fma(r[j * 4 + 3], gv[j].w, bv[j].w);
    }
}

__global__ void __launch_bounds__(NW * 32 + 32, 1)
deepnorm_kernel(const char* __restrict__ x, const char* __restrict__ f, const uint4* __restrict__ g, const uint4* __restrict__ b,
                const unsigned short* __restrict__ alpha, uint4* __restrict__ out, int rows) {
    extern __shared__ __align__(128) char smem[];
    __shared__ __align__(8) uint64_t bar[MAXROWS];
    const int cta = blockIdx.x;
    const int nrows = (rows - cta + NCTA - 1) / NCTA;
    int warp = threadIdx.x >> 5;
    const int lane = threadIdx.x & 31;
    const uint32_t sb = smem_u32(&bar[0]);
    const uint32_t sm0 = smem_u32(smem);
    if (warp == 0) {
        if (lane == 0) {
#pragma unroll
            for (int i = 0; i < MAXROWS; i++) asm volatile("mbarrier.init.shared::cta.b64 [%0], 1;" :: "r"(sb + i * 8) : "memory");
        }
        __syncwarp();
        asm volatile("bar.arrive 1, %0;" :: "r"(NW * 32 + 32) : "memory");
        if (lane == 0) {
            const char* xp = x + (size_t)cta * ROW_BYTES;
            const char* fp = f + (size_t)cta * ROW_BYTES;
            for (int r = 0; r < nrows; r++) {
                if (r >= WIN) mbar_wait(sb + (r - WIN) * 8, 0);
                mbar_expect_tx(sb + r * 8, 2 * ROW_BYTES);
                bulk_g2s(sm0 + r * 4096, xp + (size_t)r * NCTA * ROW_BYTES, ROW_BYTES, sb + r * 8);
                bulk_g2s(sm0 + r * 4096 + ROW_BYTES, fp + (size_t)r * NCTA * ROW_BYTES, ROW_BYTES, sb + r * 8);
            }
        }
        return;
    }
    uint4 gv[4], bv[4];
    const uint32_t alpha2 = (uint32_t)__ldg(alpha) * 0x10001u;
#pragma unroll
    for (int j = 0; j < 4; j++) { gv[j] = ldg_nc(g + lane + j * 32); bv[j] = ldg_nc(b + lane + j * 32); }
    asm volatile("bar.sync 1, %0;" :: "r"(NW * 32 + 32) : "memory");
    warp -= 1;
    for (int r = warp; r < nrows; r += NW) {
        mbar_wait(sb + r * 8, 0);
        const uint32_t src = sm0 + r * 4096 + lane * 16;
        uint4 xv[4], fv[4], o[4];
#pragma unroll
        for (int j = 0; j < 4; j++) { xv[j] = lds128(src + j * 512); fv[j] = lds128(src + 2048 + j * 512); }
        row_math(xv, fv, gv, bv, alpha2, o);
        uint4* op = out + (size_t)(cta + r * NCTA) * 128 + lane;
#pragma unroll
        for (int j = 0; j < 4; j++) stg(op + j * 32, o[j]);
    }
}

}

extern "C" void kernel_launch(void* const* d_in, const int* in_sizes, int n_in, void* d_out, int out_size) {
    (void)n_in; (void)out_size;
    const int rows = in_sizes[0] / D;
    static bool attr_set = false;
    if (!attr_set) {
        cudaFuncSetAttribute(deepnorm_kernel, cudaFuncAttributeMaxDynamicSharedMemorySize, MAXROWS * 4096);
        attr_set = true;
    }
    deepnorm_kernel<<<NCTA, NW * 32 + 32, MAXROWS * 4096, cudaStreamPerThread>>>(
        (const char*)d_in[0], (const char*)d_in[1], (const uint4*)d_in[2], (const uint4*)d_in[3],
        (const unsigned short*)d_in[4], (uint4*)d_out, rows);
}
```

```cpp
#include <cuda_runtime.h>
#include <cuda_bf16.h>
#include <stdint.h>

namespace {

constexpr int D         = 1024;
constexpr int ROW_BYTES = D * 2;
constexpr int NCTA      = 132;
constexpr int NW        = 8;
constexpr int PB        = 3;
constexpr int MAXROWS   = 32;
constexpr int PACE      = 310;
constexpr int SMEM_BYTES = 256 + MAXROWS * 2 * ROW_BYTES;

__device__ __forceinline__ uint32_t smem_u32(const void* p) { return (uint32_t)__cvta_generic_to_shared(p); }
__device__ __forceinline__ uint32_t clk() { uint32_t t; asm volatile("mov.u32 %0, %clock;" : "=r"(t) :: "memory"); return t; }
__device__ __forceinline__ uint4 ldg_nc(const void* p) {
    uint4 v; asm volatile("ld.global.nc.v4.u32 {%0,%1,%2,%3}, [%4];" : "=r"(v.x), "=r"(v.y), "=r"(v.z), "=r"(v.w) : "l"(p) : "memory"); return v;
}
__device__ __forceinline__ void stg(void* p, uint4 v) {
    asm volatile("st.global.v4.u32 [%4], {%0,%1,%2,%3};" :: "r"(v.x), "r"(v.y), "r"(v.z), "r"(v.w), "l"(p) : "memory");
}
__device__ __forceinline__ uint4 lds128(uint32_t a) {
    uint4 v; asm volatile("ld.shared.v4.u32 {%0,%1,%2,%3}, [%4];" : "=r"(v.x), "=r"(v.y), "=r"(v.z), "=r"(v.w) : "r"(a)); return v;
}
__device__ __forceinline__ void mbar_wait(uint32_t bar, uint32_t parity) {
    asm volatile("{\n.reg .pred p;\nWAIT_LOOP:\nmbarrier.try_wait.parity.shared::cta.b64 p, [%0], %1;\n@p bra WAIT_DONE;\nbra WAIT_LOOP;\nWAIT_DONE:\n}" :: "r"(bar), "r"(parity) : "memory");
}
__device__ __forceinline__ void fetch_row_init(uint32_t bar, uint32_t dst, const void* xs, const void* fs) {
    asm volatile("{\n.reg .pred P;\nelect.sync _|P, 0xffffffff;\n"
        "@P mbarrier.init.shared::cta.b64 [%0], 1;\n"
        "@P fence.mbarrier_init.release.cluster;\n"
        "@P mbarrier.arrive.expect_tx.shared::cta.b64 _, [%0], 4096;\n"
        "@P cp.async.bulk.shared::cluster.global.mbarrier::complete_tx::bytes [%1], [%2], 2048, [%0];\n"
        "@P cp.async.bulk.shared::cluster.global.mbarrier::complete_tx::bytes [%4], [%3], 2048, [%0];\n"
        "}\n" :: "r"(bar), "r"(dst), "l"(xs), "l"(fs), "r"(dst + 2048) : "memory");
}
__device__ __forceinline__ void fetch_row(uint32_t bar, uint32_t dst, const void* xs, const void* fs) {
    asm volatile("{\n.reg .pred P;\nelect.sync _|P, 0xffffffff;\n"
        "@P mbarrier.arrive.expect_tx.shared::cta.b64 _, [%0], 4096;\n"
        "@P cp.async.bulk.shared::cluster.global.mbarrier::complete_tx::bytes [%1], [%2], 2048, [%0];\n"
        "@P cp.async.bulk.shared::cluster.global.mbarrier::complete_tx::bytes [%4], [%3], 2048, [%0];\n"
        "}\n" :: "r"(bar), "r"(dst), "l"(xs), "l"(fs), "r"(dst + 2048) : "memory");
}
__device__ __forceinline__ uint32_t bf2_fma(uint32_t a, uint32_t b, uint32_t c) {
    uint32_t d; asm("fma.rn.bf16x2 %0, %1, %2, %3;" : "=r"(d) : "r"(a), "r"(b), "r"(c)); return d;
}
__device__ __forceinline__ float bf_lo(uint32_t v) { return __uint_as_float(v << 16); }
__device__ __forceinline__ float bf_hi(uint32_t v) { return __uint_as_float(v & 0xffff0000u); }
__device__ __forceinline__ uint32_t pack_bf2(float lo, float hi) {
    uint32_t d; asm("cvt.rn.bf16x2.f32 %0, %1, %2;" : "=r"(d) : "f"(hi), "f"(lo)); return d;
}

__device__ __forceinline__ void row_math(const uint4 (&xv)[4], const uint4 (&fv)[4], const uint4 (&gv)[4], const uint4 (&bv)[4],
                                         uint32_t alpha2, uint4 (&o)[4]) {
    uint32_t y[16];
#pragma unroll
    for (int j = 0; j < 4; j++) {
        y[j * 4 + 0] = bf2_fma(alpha2, xv[j].x, fv[j].x);
        y[j * 4 + 1] = bf2_fma(alpha2, xv[j].y, fv[j].y);
        y[j * 4 + 2] = bf2_fma(alpha2, xv[j].z, fv[j].z);
        y[j * 4 + 3] = bf2_fma(alpha2, xv[j].w, fv[j].w);
    }
    const float K = __shfl_sync(0xffffffffu, bf_lo(y[0]), 0);
    float d[32];
    float s0 = 0.f, s1 = 0.f, q0 = 0.f, q1 = 0.f;
#pragma unroll
    for (int i = 0; i < 16; i++) {
        const float a = bf_lo(y[i]) - K, c = bf_hi(y[i]) - K;
        d[2 * i] = a; d[2 * i + 1] = c;
        s0 += a; s1 += c;
        q0 = fmaf(a, a, q0); q1 = fmaf(c, c, q1);
    }
    float s = s0 + s1, q = q0 + q1;
#pragma unroll
    for (int m = 16; m >= 1; m >>= 1) {
        s += __shfl_xor_sync(0xffffffffu, s, m);
        q += __shfl_xor_sync(0xffffffffu, q, m);
    }
    const float mean = s * (1.0f / D);
    const float var  = fmaxf(fmaf(-mean, mean, q * (1.0f / D)), 0.f);
    const float rstd = rsqrtf(var + 1e-5f);
    const float nb   = -mean * rstd;
#pragma unroll
    for (int j = 0; j < 4; j++) {
        o[j].x = bf2_fma(pack_bf2(fmaf(d[8 * j + 0], rstd, nb), fmaf(d[8 * j + 1], rstd, nb)), gv[j].x, bv[j].x);
        o[j].y = bf2_fma(pack_bf2(fmaf(d[8 * j + 2], rstd, nb), fmaf(d[8 * j + 3], rstd, nb)), gv[j].y, bv[j].y);
        o[j].z = bf2_fma(pack_bf2(fmaf(d[8 * j + 4], rstd, nb), fmaf(d[8 * j + 5], rstd, nb)), gv[j].z, bv[j].z);
        o[j].w = bf2_fma(pack_bf2(fmaf(d[8 * j + 6], rstd, nb), fmaf(d[8 * j + 7], rstd, nb)), gv[j].w, bv[j].w);
    }
}

__global__ void __launch_bounds__(NW * 32 + 32, 1)
deepnorm_kernel(const char* __restrict__ x, const char* __restrict__ f, const uint4* __restrict__ g, const uint4* __restrict__ b,
                const void* __restrict__ alpha, uint4* __restrict__ out, int rows) {
    extern __shared__ __align__(128) char smem[];
    const uint32_t c0 = clk();
    const int cta = blockIdx.x;
    const uint32_t sb  = smem_u32(smem);
    const uint32_t sm0 = sb + 256;
    const char* xp = x + (size_t)cta * ROW_BYTES;
    const char* fp = f + (size_t)cta * ROW_BYTES;
    asm volatile("{\n.reg .pred P, Q;\nelect.sync _|Q, 0xffffffff;\nsetp.lt.and.u32 P, %5, 32, Q;\n"
        "@P mbarrier.init.shared::cta.b64 [%0], 1;\n"
        "@P fence.mbarrier_init.release.cluster;\n"
        "@P mbarrier.arrive.expect_tx.shared::cta.b64 _, [%0], 4096;\n"
        "@P cp.async.bulk.shared::cluster.global.mbarrier::complete_tx::bytes [%1], [%2], 2048, [%0];\n"
        "@P cp.async.bulk.shared::cluster.global.mbarrier::complete_tx::bytes [%4], [%3], 2048, [%0];\n"
        "}\n" :: "r"(sb), "r"(sm0), "l"(xp), "l"(fp), "r"(sm0 + 2048), "r"(threadIdx.x) : "memory");
    const int nrows = (rows - cta + NCTA - 1) / NCTA;
    const int wid = __shfl_sync(0xffffffffu, threadIdx.x >> 5, 0);
    if (wid == 0) {
        uint32_t tgt = 0, bar = sb, dst = sm0;
#pragma unroll
        for (int r = 1; r < PB; r++) {
            xp += NCTA * ROW_BYTES; fp += NCTA * ROW_BYTES; bar += 8; dst += 2 * ROW_BYTES;
            tgt += PACE;
            while (clk() - c0 < tgt) { }
            fetch_row_init(bar, dst, xp, fp);
        }
        asm volatile("bar.sync 1, %0;" :: "n"(NW * 32 + 32) : "memory");
#pragma unroll 1
        for (int r = PB; r < nrows; r++) {
            xp += NCTA * ROW_BYTES; fp += NCTA * ROW_BYTES; bar += 8; dst += 2 * ROW_BYTES;
            tgt += PACE;
            while (clk() - c0 < tgt) { }
            fetch_row(bar, dst, xp, fp);
        }
        return;
    }
    const int lane = threadIdx.x & 31;
    const int warp = wid - 1;
    {
        static_assert(NW == 8 && MAXROWS == 32, "barrier init pattern");
        const uint32_t b0 = sb + warp * 8;
        asm volatile("{\n.reg .pred P, Q;\nelect.sync _|P, 0xffffffff;\nsetp.ge.and.u32 Q, %1, %2, P;\n"
            "@Q mbarrier.init.shared::cta.b64 [%0], 1;\n"
            "@P mbarrier.init.shared::cta.b64 [%0+64], 1;\n"
            "@P mbarrier.init.shared::cta.b64 [%0+128], 1;\n"
            "@P mbarrier.init.shared::cta.b64 [%0+192], 1;\n"
            "@P fence.mbarrier_init.release.cluster;\n}\n" :: "r"(b0), "r"(warp), "n"(PB) : "memory");
    }
    uint4 gv[4], bv[4];
    uint32_t alpha_raw;
    asm volatile("ld.global.nc.u16 %0, [%1];" : "=r"(alpha_raw) : "l"(alpha) : "memory");
#pragma unroll
    for (int j = 0; j < 4; j++) { gv[j] = ldg_nc(g + lane + j * 32); bv[j] = ldg_nc(b + lane + j * 32); }
    asm volatile("bar.sync 1, %0;" :: "n"(NW * 32 + 32) : "memory");
    int r = warp;
    do {
        mbar_wait(sb + r * 8, 0);
        const uint32_t src = sm0 + r * (2 * ROW_BYTES) + lane * 16;
        uint4 xv[4], fv[4], o[4];
#pragma unroll
        for (int j = 0; j < 4; j++) { xv[j] = lds128(src + j * 512); fv[j] = lds128(src + ROW_BYTES + j * 512); }
        uint32_t alpha2; asm volatile("prmt.b32 %0, %1, %1, 0x1010;" : "=r"(alpha2) : "r"(alpha_raw));
        row_math(xv, fv, gv, bv, alpha2, o);
        uint4* op = out + (size_t)(cta + r * NCTA) * 128 + lane;
#pragma unroll
        for (int j = 0; j < 4; j++) stg(op + j * 32, o[j]);
        r += NW;
    } while (r < nrows);
}

}

extern "C" void kernel_launch(void* const* d_in, const int* in_sizes, int n_in, void* d_out, int out_size) {
    (void)n_in; (void)out_size;
    const int rows = in_sizes[0] / D;
    static bool attr_set = false;
    if (!attr_set) {
        cudaFuncSetAttribute(deepnorm_kernel, cudaFuncAttributeMaxDynamicSharedMemorySize, SMEM_BYTES);
        attr_set = true;
    }
    deepnorm_kernel<<<NCTA, NW * 32 + 32, SMEM_BYTES, cudaStreamPerThread>>>(
        (const char*)d_in[0], (const char*)d_in[1], (const uint4*)d_in[2], (const uint4*)d_in[3],
        d_in[4], (uint4*)d_out, rows);
}
```

```cpp
#include <cuda_runtime.h>
#include <cuda_bf16.h>
#include <stdint.h>

namespace {

constexpr int D         = 1024;
constexpr int ROW_BYTES = D * 2;
constexpr int NCTA      = 128;
constexpr int NROWS     = 32;
constexpr int NW        = 8;
constexpr int PB        = 3;
constexpr int PACE      = 295;
constexpr int HOLD      = 18;
constexpr int REL_PARK  = 29;
constexpr int REL_LAST  = 30;
constexpr int SMEM_BYTES = 256 + NROWS * 2 * ROW_BYTES;

__device__ __forceinline__ uint32_t smem_u32(const void* p) { return (uint32_t)__cvta_generic_to_shared(p); }
__device__ __forceinline__ uint32_t clk() { uint32_t t; asm volatile("mov.u32 %0, %clock;" : "=r"(t) :: "memory"); return t; }
__device__ __forceinline__ uint4 ldg_nc(const void* p) {
    uint4 v; asm volatile("ld.global.nc.v4.u32 {%0,%1,%2,%3}, [%4];" : "=r"(v.x), "=r"(v.y), "=r"(v.z), "=r"(v.w) : "l"(p) : "memory"); return v;
}
__device__ __forceinline__ void stg(void* p, uint4 v) {
    asm volatile("st.global.v4.u32 [%4], {%0,%1,%2,%3};" :: "r"(v.x), "r"(v.y), "r"(v.z), "r"(v.w), "l"(p) : "memory");
}
__device__ __forceinline__ uint4 lds128(uint32_t a) {
    uint4 v; asm volatile("ld.shared.v4.u32 {%0,%1,%2,%3}, [%4];" : "=r"(v.x), "=r"(v.y), "=r"(v.z), "=r"(v.w) : "r"(a) : "memory"); return v;
}
__device__ __forceinline__ void sts128(uint32_t a, uint4 v) {
    asm volatile("st.shared.v4.u32 [%4], {%0,%1,%2,%3};" :: "r"(v.x), "r"(v.y), "r"(v.z), "r"(v.w), "r"(a) : "memory");
}
__device__ __forceinline__ void mbar_wait(uint32_t bar) {
    asm volatile("{\n.reg .pred p;\nWAIT_LOOP:\nmbarrier.try_wait.parity.shared::cta.b64 p, [%0], 0;\n@p bra WAIT_DONE;\nbra WAIT_LOOP;\nWAIT_DONE:\n}" :: "r"(bar) : "memory");
}
__device__ __forceinline__ void fetch_row_init(uint32_t bar, uint32_t dst, const void* xs, const void* fs) {
    asm volatile("{\n.reg .pred P;\nelect.sync _|P, 0xffffffff;\n"
        "@P mbarrier.init.shared::cta.b64 [%0], 1;\n"
        "@P fence.mbarrier_init.release.cluster;\n"
        "@P mbarrier.arrive.expect_tx.shared::cta.b64 _, [%0], 4096;\n"
        "@P cp.async.bulk.shared::cluster.global.mbarrier::complete_tx::bytes [%1], [%2], 2048, [%0];\n"
        "@P cp.async.bulk.shared::cluster.global.mbarrier::complete_tx::bytes [%4], [%3], 2048, [%0];\n"
        "}\n" :: "r"(bar), "r"(dst), "l"(xs), "l"(fs), "r"(dst + 2048) : "memory");
}
__device__ __forceinline__ void fetch_row(uint32_t bar, uint32_t dst, const void* xs, const void* fs) {
    asm volatile("{\n.reg .pred P;\nelect.sync _|P, 0xffffffff;\n"
        "@P mbarrier.arrive.expect_tx.shared::cta.b64 _, [%0], 4096;\n"
        "@P cp.async.bulk.shared::cluster.global.mbarrier::complete_tx::bytes [%1], [%2], 2048, [%0];\n"
        "@P cp.async.bulk.shared::cluster.global.mbarrier::complete_tx::bytes [%4], [%3], 2048, [%0];\n"
        "}\n" :: "r"(bar), "r"(dst), "l"(xs), "l"(fs), "r"(dst + 2048) : "memory");
}
__device__ __forceinline__ uint32_t bf2_fma(uint32_t a, uint32_t b, uint32_t c) {
    uint32_t d; asm("fma.rn.bf16x2 %0, %1, %2, %3;" : "=r"(d) : "r"(a), "r"(b), "r"(c)); return d;
}
__device__ __forceinline__ float bf_lo(uint32_t v) { return __uint_as_float(v << 16); }
__device__ __forceinline__ float bf_hi(uint32_t v) { return __uint_as_float(v & 0xffff0000u); }
__device__ __forceinline__ uint32_t pack_bf2(float lo, float hi) {
    uint32_t d; asm("cvt.rn.bf16x2.f32 %0, %1, %2;" : "=r"(d) : "f"(hi), "f"(lo)); return d;
}

__device__ __forceinline__ void row_math(const uint4 (&xv)[4], const uint4 (&fv)[4], const uint4 (&gv)[4], const uint4 (&bv)[4],
                                         uint32_t alpha2, uint4 (&o)[4]) {
    uint32_t y[16];
#pragma unroll
    for (int j = 0; j < 4; j++) {
        y[j * 4 + 0] = bf2_fma(alpha2, xv[j].x, fv[j].x);
        y[j * 4 + 1] = bf2_fma(alpha2, xv[j].y, fv[j].y);
        y[j * 4 + 2] = bf2_fma(alpha2, xv[j].z, fv[j].z);
        y[j * 4 + 3] = bf2_fma(alpha2, xv[j].w, fv[j].w);
    }
    const float K = __shfl_sync(0xffffffffu, bf_lo(y[0]), 0);
    float d[32];
    float s0 = 0.f, s1 = 0.f, q0 = 0.f, q1 = 0.f;
#pragma unroll
    for (int i = 0; i < 16; i++) {
        const float a = bf_lo(y[i]) - K, c = bf_hi(y[i]) - K;
        d[2 * i] = a; d[2 * i + 1] = c;
        s0 += a; s1 += c;
        q0 = fmaf(a, a, q0); q1 = fmaf(c, c, q1);
    }
    float s = s0 + s1, q = q0 + q1;
#pragma unroll
    for (int m = 16; m >= 1; m >>= 1) {
        s += __shfl_xor_sync(0xffffffffu, s, m);
        q += __shfl_xor_sync(0xffffffffu, q, m);
    }
    const float mean = s * (1.0f / D);
    const float var  = fmaxf(fmaf(-mean, mean, q * (1.0f / D)), 0.f) + 1e-5f;
    float rstd; asm("rsqrt.approx.ftz.f32 %0, %1;" : "=f"(rstd) : "f"(var));
    const float nb = -mean * rstd;
#pragma unroll
    for (int j = 0; j < 4; j++) {
        o[j].x = bf2_fma(pack_bf2(fmaf(d[8 * j + 0], rstd, nb), fmaf(d[8 * j + 1], rstd, nb)), gv[j].x, bv[j].x);
        o[j].y = bf2_fma(pack_bf2(fmaf(d[8 * j + 2], rstd, nb), fmaf(d[8 * j + 3], rstd, nb)), gv[j].y, bv[j].y);
        o[j].z = bf2_fma(pack_bf2(fmaf(d[8 * j + 4], rstd, nb), fmaf(d[8 * j + 5], rstd, nb)), gv[j].z, bv[j].z);
        o[j].w = bf2_fma(pack_bf2(fmaf(d[8 * j + 6], rstd, nb), fmaf(d[8 * j + 7], rstd, nb)), gv[j].w, bv[j].w);
    }
}

__global__ void __launch_bounds__(NW * 32 + 32, 1)
deepnorm_kernel(const char* __restrict__ x, const char* __restrict__ f, const uint4* __restrict__ g, const uint4* __restrict__ b,
                const void* __restrict__ alpha, uint4* __restrict__ out) {
    extern __shared__ __align__(128) char smem[];
    const uint32_t c0 = clk();
    const int cta = blockIdx.x;
    const uint32_t sb  = smem_u32(smem);
    const uint32_t sm0 = sb + 256;
    const char* xp = x + (size_t)cta * ROW_BYTES;
    const char* fp = f + (size_t)cta * ROW_BYTES;
    asm volatile("{\n.reg .pred P, Q;\nelect.sync _|Q, 0xffffffff;\nsetp.lt.and.u32 P, %5, 32, Q;\n"
        "@P mbarrier.init.shared::cta.b64 [%0], 1;\n"
        "@P fence.mbarrier_init.release.cluster;\n"
        "@P mbarrier.arrive.expect_tx.shared::cta.b64 _, [%0], 4096;\n"
        "@P cp.async.bulk.shared::cluster.global.mbarrier::complete_tx::bytes [%1], [%2], 2048, [%0];\n"
        "@P cp.async.bulk.shared::cluster.global.mbarrier::complete_tx::bytes [%4], [%3], 2048, [%0];\n"
        "}\n" :: "r"(sb), "r"(sm0), "l"(xp), "l"(fp), "r"(sm0 + 2048), "r"(threadIdx.x) : "memory");
    const int wid = __shfl_sync(0xffffffffu, threadIdx.x >> 5, 0);
    if (wid == 0) {
        uint32_t tgt = c0, bar = sb, dst = sm0;
#pragma unroll
        for (int r = 1; r < PB; r++) {
            xp += NCTA * ROW_BYTES; fp += NCTA * ROW_BYTES; bar += 8; dst += 2 * ROW_BYTES;
            tgt += PACE;
            while ((int)(tgt - clk()) > 0) { }
            fetch_row_init(bar, dst, xp, fp);
        }
        asm volatile("bar.sync 1, %0;" :: "n"(NW * 32 + 32) : "memory");
#pragma unroll 1
        for (int r = PB; r < NROWS; r++) {
            xp += NCTA * ROW_BYTES; fp += NCTA * ROW_BYTES; bar += 8; dst += 2 * ROW_BYTES;
            tgt += PACE;
            while ((int)(tgt - clk()) > 0) { }
            fetch_row(bar, dst, xp, fp);
        }
        return;
    }
    const int lane = threadIdx.x & 31;
    const int warp = wid - 1;
    {
        static_assert(NW == 8 && NROWS == 32, "barrier init pattern");
        const uint32_t b0 = sb + warp * 8;
        asm volatile("{\n.reg .pred P, Q;\nelect.sync _|P, 0xffffffff;\nsetp.ge.and.u32 Q, %1, %2, P;\n"
            "@Q mbarrier.init.shared::cta.b64 [%0], 1;\n"
            "@P mbarrier.init.shared::cta.b64 [%0+64], 1;\n"
            "@P mbarrier.init.shared::cta.b64 [%0+128], 1;\n"
            "@P mbarrier.init.shared::cta.b64 [%0+192], 1;\n"
            "@P fence.mbarrier_init.release.cluster;\n}\n" :: "r"(b0), "r"(warp), "n"(PB) : "memory");
    }
    uint4 gv[4], bv[4];
    uint32_t alpha_raw;
    asm volatile("ld.global.nc.u16 %0, [%1];" : "=r"(alpha_raw) : "l"(alpha) : "memory");
#pragma unroll
    for (int j = 0; j < 4; j++) { gv[j] = ldg_nc(g + lane + j * 32); bv[j] = ldg_nc(b + lane + j * 32); }
    asm volatile("bar.sync 1, %0;" :: "n"(NW * 32 + 32) : "memory");
    int r = warp;
#pragma unroll 1
    do {
        mbar_wait(sb + r * 8);
        const uint32_t src = sm0 + r * (2 * ROW_BYTES) + lane * 16;
        uint4 xv[4], fv[4], o[4];
#pragma unroll
        for (int j = 0; j < 4; j++) { xv[j] = lds128(src + j * 512); fv[j] = lds128(src + ROW_BYTES + j * 512); }
        uint32_t alpha2; asm volatile("prmt.b32 %0, %1, %1, 0x1010;" : "=r"(alpha2) : "r"(alpha_raw));
        row_math(xv, fv, gv, bv, alpha2, o);
        uint4* op = out + (size_t)(cta + r * NCTA) * (ROW_BYTES / 16) + lane;
        if (r < NROWS - NW) {
            if (r >= HOLD) {
#pragma unroll
                for (int j = 0; j < 4; j++) sts128(src + j * 512, o[j]);
            } else {
#pragma unroll
                for (int j = 0; j < 4; j++) stg(op + j * 32, o[j]);
            }
        } else {
            if (r - NW >= HOLD) {
                mbar_wait(sb + REL_PARK * 8);
                uint4 t[4];
#pragma unroll
                for (int j = 0; j < 4; j++) t[j] = lds128(src - NW * 2 * ROW_BYTES + j * 512);
#pragma unroll
                for (int j = 0; j < 4; j++) stg(op - NW * NCTA * (ROW_BYTES / 16) + j * 32, t[j]);
            }
            if (r < REL_LAST) mbar_wait(sb + REL_LAST * 8);
#pragma unroll
            for (int j = 0; j < 4; j++) stg(op + j * 32, o[j]);
        }
        r += NW;
    } while (r < NROWS);
}

}

extern "C" void kernel_launch(void* const* d_in, const int* in_sizes, int n_in, void* d_out, int out_size) {
    (void)in_sizes; (void)n_in; (void)out_size;
    static bool attr_set = false;
    if (!attr_set) {
        cudaFuncSetAttribute(deepnorm_kernel, cudaFuncAttributeMaxDynamicSharedMemorySize, SMEM_BYTES);
        attr_set = true;
    }
    deepnorm_kernel<<<NCTA, NW * 32 + 32, SMEM_BYTES, cudaStreamPerThread>>>(
        (const char*)d_in[0], (const char*)d_in[1], (const uint4*)d_in[2], (const uint4*)d_in[3],
        d_in[4], (uint4*)d_out);
}
```

```cpp
#include <cuda_runtime.h>
#include <cuda_bf16.h>
#include <stdint.h>

namespace {

constexpr int D         = 1024;
constexpr int ROW_BYTES = D * 2;
constexpr int NCTA      = 128;
constexpr int NROWS     = 32;
constexpr int NW        = 8;
constexpr int PB        = 3;
constexpr int PACE      = 295;
constexpr int LEAD      = 128;
constexpr int HOLD      = 16;
constexpr int REL_PARK  = 28;
constexpr int REL_LAST  = 29;
constexpr int SMEM_BYTES = 256 + NROWS * 2 * ROW_BYTES;

__device__ __forceinline__ uint32_t smem_u32(const void* p) { return (uint32_t)__cvta_generic_to_shared(p); }
__device__ __forceinline__ uint32_t clk() { uint32_t t; asm volatile("mov.u32 %0, %clock;" : "=r"(t) :: "memory"); return t; }
__device__ __forceinline__ uint4 ldg_nc(const void* p) {
    uint4 v; asm volatile("ld.global.nc.v4.u32 {%0,%1,%2,%3}, [%4];" : "=r"(v.x), "=r"(v.y), "=r"(v.z), "=r"(v.w) : "l"(p) : "memory"); return v;
}
__device__ __forceinline__ void stg(void* p, uint4 v) {
    asm volatile("st.global.v4.u32 [%4], {%0,%1,%2,%3};" :: "r"(v.x), "r"(v.y), "r"(v.z), "r"(v.w), "l"(p) : "memory");
}
__device__ __forceinline__ uint4 lds128(uint32_t a) {
    uint4 v; asm volatile("ld.shared.v4.u32 {%0,%1,%2,%3}, [%4];" : "=r"(v.x), "=r"(v.y), "=r"(v.z), "=r"(v.w) : "r"(a) : "memory"); return v;
}
__device__ __forceinline__ void sts128(uint32_t a, uint4 v) {
    asm volatile("st.shared.v4.u32 [%4], {%0,%1,%2,%3};" :: "r"(v.x), "r"(v.y), "r"(v.z), "r"(v.w), "r"(a) : "memory");
}
__device__ __forceinline__ void mbar_wait(uint32_t bar) {
    asm volatile("{\n.reg .pred p;\nWAIT_LOOP:\nmbarrier.try_wait.parity.shared::cta.b64 p, [%0], 0;\n@p bra WAIT_DONE;\nbra WAIT_LOOP;\nWAIT_DONE:\n}" :: "r"(bar) : "memory");
}
__device__ __forceinline__ void fetch_row_init(uint32_t bar, uint32_t dst, const void* xs, const void* fs) {
    asm volatile("{\n.reg .pred P;\nelect.sync _|P, 0xffffffff;\n"
        "@P mbarrier.init.shared::cta.b64 [%0], 1;\n"
        "@P fence.mbarrier_init.release.cluster;\n"
        "@P mbarrier.arrive.expect_tx.shared::cta.b64 _, [%0], 4096;\n"
        "@P cp.async.bulk.shared::cluster.global.mbarrier::complete_tx::bytes [%1], [%2], 2048, [%0];\n"
        "@P cp.async.bulk.shared::cluster.global.mbarrier::complete_tx::bytes [%4], [%3], 2048, [%0];\n"
        "}\n" :: "r"(bar), "r"(dst), "l"(xs), "l"(fs), "r"(dst + 2048) : "memory");
}
__device__ __forceinline__ void fetch_row(uint32_t bar, uint32_t dst, const void* xs, const void* fs) {
    asm volatile("{\n.reg .pred P;\nelect.sync _|P, 0xffffffff;\n"
        "@P mbarrier.arrive.expect_tx.shared::cta.b64 _, [%0], 4096;\n"
        "@P cp.async.bulk.shared::cluster.global.mbarrier::complete_tx::bytes [%1], [%2], 2048, [%0];\n"
        "@P cp.async.bulk.shared::cluster.global.mbarrier::complete_tx::bytes [%4], [%3], 2048, [%0];\n"
        "}\n" :: "r"(bar), "r"(dst), "l"(xs), "l"(fs), "r"(dst + 2048) : "memory");
}
__device__ __forceinline__ uint32_t bf2_fma(uint32_t a, uint32_t b, uint32_t c) {
    uint32_t d; asm("fma.rn.bf16x2 %0, %1, %2, %3;" : "=r"(d) : "r"(a), "r"(b), "r"(c)); return d;
}
__device__ __forceinline__ float bf_lo(uint32_t v) { return __uint_as_float(v << 16); }
__device__ __forceinline__ float bf_hi(uint32_t v) { return __uint_as_float(v & 0xffff0000u); }
__device__ __forceinline__ uint32_t pack_bf2(float lo, float hi) {
    uint32_t d; asm("cvt.rn.bf16x2.f32 %0, %1, %2;" : "=r"(d) : "f"(hi), "f"(lo)); return d;
}

__device__ __forceinline__ void row_math(const uint4 (&xv)[4], const uint4 (&fv)[4], const uint4 (&gv)[4], const uint4 (&bv)[4],
                                         uint32_t alpha2, uint4 (&o)[4]) {
    uint32_t y[16];
#pragma unroll
    for (int j = 0; j < 4; j++) {
        y[j * 4 + 0] = bf2_fma(alpha2, xv[j].x, fv[j].x);
        y[j * 4 + 1] = bf2_fma(alpha2, xv[j].y, fv[j].y);
        y[j * 4 + 2] = bf2_fma(alpha2, xv[j].z, fv[j].z);
        y[j * 4 + 3] = bf2_fma(alpha2, xv[j].w, fv[j].w);
    }
    const float K = __shfl_sync(0xffffffffu, bf_lo(y[0]), 0);
    float d[32];
    float s0 = 0.f, s1 = 0.f, q0 = 0.f, q1 = 0.f;
#pragma unroll
    for (int i = 0; i < 16; i++) {
        const float a = bf_lo(y[i]) - K, c = bf_hi(y[i]) - K;
        d[2 * i] = a; d[2 * i + 1] = c;
        s0 += a; s1 += c;
        q0 = fmaf(a, a, q0); q1 = fmaf(c, c, q1);
    }
    float s = s0 + s1, q = q0 + q1;
#pragma unroll
    for (int m = 16; m >= 1; m >>= 1) {
        s += __shfl_xor_sync(0xffffffffu, s, m);
        q += __shfl_xor_sync(0xffffffffu, q, m);
    }
    const float mean = s * (1.0f / D);
    const float var  = fmaxf(fmaf(-mean, mean, q * (1.0f / D)), 0.f) + 1e-5f;
    float rstd; asm("rsqrt.approx.ftz.f32 %0, %1;" : "=f"(rstd) : "f"(var));
    const float nb = -mean * rstd;
#pragma unroll
    for (int j = 0; j < 4; j++) {
        o[j].x = bf2_fma(pack_bf2(fmaf(d[8 * j + 0], rstd, nb), fmaf(d[8 * j + 1], rstd, nb)), gv[j].x, bv[j].x);
        o[j].y = bf2_fma(pack_bf2(fmaf(d[8 * j + 2], rstd, nb), fmaf(d[8 * j + 3], rstd, nb)), gv[j].y, bv[j].y);
        o[j].z = bf2_fma(pack_bf2(fmaf(d[8 * j + 4], rstd, nb), fmaf(d[8 * j + 5], rstd, nb)), gv[j].z, bv[j].z);
        o[j].w = bf2_fma(pack_bf2(fmaf(d[8 * j + 6], rstd, nb), fmaf(d[8 * j + 7], rstd, nb)), gv[j].w, bv[j].w);
    }
}

__device__ __forceinline__ void release_parked(uint32_t src, uint4* dst) {
    uint4 t[4];
#pragma unroll
    for (int j = 0; j < 4; j++) t[j] = lds128(src + j * 512);
#pragma unroll
    for (int j = 0; j < 4; j++) stg(dst + j * 32, t[j]);
}

__global__ void __launch_bounds__(NW * 32 + 32, 1)
deepnorm_kernel(const char* __restrict__ x, const char* __restrict__ f, const uint4* __restrict__ g, const uint4* __restrict__ b,
                const void* __restrict__ alpha, uint4* __restrict__ out) {
    extern __shared__ __align__(128) char smem[];
    const uint32_t c0 = clk() - LEAD;
    const int cta = blockIdx.x;
    const uint32_t sb  = smem_u32(smem);
    const uint32_t sm0 = sb + 256;
    const char* xp = x + (size_t)cta * ROW_BYTES;
    const char* fp = f + (size_t)cta * ROW_BYTES;
    asm volatile("{\n.reg .pred P, Q;\nelect.sync _|Q, 0xffffffff;\nsetp.lt.and.u32 P, %5, 32, Q;\n"
        "@P mbarrier.init.shared::cta.b64 [%0], 1;\n"
        "@P fence.mbarrier_init.release.cluster;\n"
        "@P mbarrier.arrive.expect_tx.shared::cta.b64 _, [%0], 4096;\n"
        "@P cp.async.bulk.shared::cluster.global.mbarrier::complete_tx::bytes [%1], [%2], 2048, [%0];\n"
        "@P cp.async.bulk.shared::cluster.global.mbarrier::complete_tx::bytes [%4], [%3], 2048, [%0];\n"
        "}\n" :: "r"(sb), "r"(sm0), "l"(xp), "l"(fp), "r"(sm0 + 2048), "r"(threadIdx.x) : "memory");
    const int wid = __shfl_sync(0xffffffffu, threadIdx.x >> 5, 0);
    if (wid == 0) {
        uint32_t tgt = c0, bar = sb, dst = sm0;
#pragma unroll
        for (int r = 1; r < PB; r++) {
            xp += NCTA * ROW_BYTES; fp += NCTA * ROW_BYTES; bar += 8; dst += 2 * ROW_BYTES;
            tgt += PACE;
            while ((int)(tgt - clk()) > 0) { }
            fetch_row_init(bar, dst, xp, fp);
        }
        asm volatile("bar.sync 1, %0;" :: "n"(NW * 32 + 32) : "memory");
#pragma unroll 1
        for (int r = PB; r < NROWS; r++) {
            xp += NCTA * ROW_BYTES; fp += NCTA * ROW_BYTES; bar += 8; dst += 2 * ROW_BYTES;
            tgt += PACE;
            while ((int)(tgt - clk()) > 0) { }
            fetch_row(bar, dst, xp, fp);
        }
        return;
    }
    const int lane = threadIdx.x & 31;
    const int warp = wid - 1;
    {
        static_assert(NW == 8 && NROWS == 32, "barrier init pattern");
        const uint32_t b0 = sb + warp * 8;
        asm volatile("{\n.reg .pred P, Q;\nelect.sync _|P, 0xffffffff;\nsetp.ge.and.u32 Q, %1, %2, P;\n"
            "@Q mbarrier.init.shared::cta.b64 [%0], 1;\n"
            "@P mbarrier.init.shared::cta.b64 [%0+64], 1;\n"
            "@P mbarrier.init.shared::cta.b64 [%0+128], 1;\n"
            "@P mbarrier.init.shared::cta.b64 [%0+192], 1;\n"
            "@P fence.mbarrier_init.release.cluster;\n}\n" :: "r"(b0), "r"(warp), "n"(PB) : "memory");
    }
    uint4 gv[4], bv[4];
    uint32_t alpha_raw;
    asm volatile("ld.global.nc.u16 %0, [%1];" : "=r"(alpha_raw) : "l"(alpha) : "memory");
#pragma unroll
    for (int j = 0; j < 4; j++) { gv[j] = ldg_nc(g + lane + j * 32); bv[j] = ldg_nc(b + lane + j * 32); }
    asm volatile("bar.sync 1, %0;" :: "n"(NW * 32 + 32) : "memory");
    int r = warp;
#pragma unroll 1
    do {
        const uint32_t src = sm0 + r * (2 * ROW_BYTES) + lane * 16;
        uint4* op = out + (size_t)(cta + r * NCTA) * (ROW_BYTES / 16) + lane;
        const bool last   = r >= NROWS - NW;
        const bool parked = last && (r - NW >= HOLD);
        if (parked && r > REL_PARK) {
            mbar_wait(sb + REL_PARK * 8);
            release_parked(src - NW * 2 * ROW_BYTES, op - NW * NCTA * (ROW_BYTES / 16));
        }
        mbar_wait(sb + r * 8);
        uint4 xv[4], fv[4], o[4];
#pragma unroll
        for (int j = 0; j < 4; j++) { xv[j] = lds128(src + j * 512); fv[j] = lds128(src + ROW_BYTES + j * 512); }
        uint32_t alpha2; asm volatile("prmt.b32 %0, %1, %1, 0x1010;" : "=r"(alpha2) : "r"(alpha_raw));
        row_math(xv, fv, gv, bv, alpha2, o);
        if (!last && r >= HOLD) {
#pragma unroll
            for (int j = 0; j < 4; j++) sts128(src + j * 512, o[j]);
        } else {
            if (parked && r <= REL_PARK) {
                mbar_wait(sb + REL_PARK * 8);
                release_parked(src - NW * 2 * ROW_BYTES, op - NW * NCTA * (ROW_BYTES / 16));
            }
            if (last && r < REL_LAST) mbar_wait(sb + REL_LAST * 8);
#pragma unroll
            for (int j = 0; j < 4; j++) stg(op + j * 32, o[j]);
        }
        r += NW;
    } while (r < NROWS);
}

}

extern "C" void kernel_launch(void* const* d_in, const int* in_sizes, int n_in, void* d_out, int out_size) {
    (void)in_sizes; (void)n_in; (void)out_size;
    static bool attr_set = false;
    if (!attr_set) {
        cudaFuncSetAttribute(deepnorm_kernel, cudaFuncAttributeMaxDynamicSharedMemorySize, SMEM_BYTES);
        attr_set = true;
    }
    deepnorm_kernel<<<NCTA, NW * 32 + 32, SMEM_BYTES, cudaStreamPerThread>>>(
        (const char*)d_in[0], (const char*)d_in[1], (const uint4*)d_in[2], (const uint4*)d_in[3],
        d_in[4], (uint4*)d_out);
}
```

```cpp
#include <cuda_runtime.h>
#include <cuda_bf16.h>
#include <stdint.h>

namespace {

constexpr int D         = 1024;
constexpr int ROW_BYTES = D * 2;
constexpr int NCTA      = 128;
constexpr int NROWS     = 32;
constexpr int NW        = 8;
constexpr int PB        = 3;
constexpr int PACE      = 295;
constexpr int LEAD      = 128;
constexpr int HOLD      = 16;
constexpr int REL_PARK  = 27;
constexpr int REL_LAST  = 29;
constexpr int SMEM_BYTES = 256 + NROWS * 2 * ROW_BYTES;

__device__ __forceinline__ uint32_t smem_u32(const void* p) { return (uint32_t)__cvta_generic_to_shared(p); }
__device__ __forceinline__ uint32_t clk() { uint32_t t; asm volatile("mov.u32 %0, %clock;" : "=r"(t) :: "memory"); return t; }
__device__ __forceinline__ uint4 ldg_nc(const void* p) {
    uint4 v; asm volatile("ld.global.nc.v4.u32 {%0,%1,%2,%3}, [%4];" : "=r"(v.x), "=r"(v.y), "=r"(v.z), "=r"(v.w) : "l"(p) : "memory"); return v;
}
__device__ __forceinline__ void stg(void* p, uint4 v) {
    asm volatile("st.global.v4.u32 [%4], {%0,%1,%2,%3};" :: "r"(v.x), "r"(v.y), "r"(v.z), "r"(v.w), "l"(p) : "memory");
}
__device__ __forceinline__ uint4 lds128(uint32_t a) {
    uint4 v; asm volatile("ld.shared.v4.u32 {%0,%1,%2,%3}, [%4];" : "=r"(v.x), "=r"(v.y), "=r"(v.z), "=r"(v.w) : "r"(a) : "memory"); return v;
}
__device__ __forceinline__ void sts128(uint32_t a, uint4 v) {
    asm volatile("st.shared.v4.u32 [%4], {%0,%1,%2,%3};" :: "r"(v.x), "r"(v.y), "r"(v.z), "r"(v.w), "r"(a) : "memory");
}
__device__ __forceinline__ void mbar_wait(uint32_t bar) {
    asm volatile("{\n.reg .pred p;\nWAIT_LOOP:\nmbarrier.try_wait.parity.shared::cta.b64 p, [%0], 0;\n@p bra WAIT_DONE;\nbra WAIT_LOOP;\nWAIT_DONE:\n}" :: "r"(bar) : "memory");
}
__device__ __forceinline__ void fetch_row_init(uint32_t bar, uint32_t dst, const void* xs, const void* fs) {
    asm volatile("{\n.reg .pred P;\nelect.sync _|P, 0xffffffff;\n"
        "@P mbarrier.init.shared::cta.b64 [%0], 1;\n"
        "@P fence.mbarrier_init.release.cluster;\n"
        "@P mbarrier.arrive.expect_tx.shared::cta.b64 _, [%0], 4096;\n"
        "@P cp.async.bulk.shared::cluster.global.mbarrier::complete_tx::bytes [%1], [%2], 2048, [%0];\n"
        "@P cp.async.bulk.shared::cluster.global.mbarrier::complete_tx::bytes [%4], [%3], 2048, [%0];\n"
        "}\n" :: "r"(bar), "r"(dst), "l"(xs), "l"(fs), "r"(dst + 2048) : "memory");
}
__device__ __forceinline__ void fetch_row(uint32_t bar, uint32_t dst, const void* xs, const void* fs) {
    asm volatile("{\n.reg .pred P;\nelect.sync _|P, 0xffffffff;\n"
        "@P mbarrier.arrive.expect_tx.shared::cta.b64 _, [%0], 4096;\n"
        "@P cp.async.bulk.shared::cluster.global.mbarrier::complete_tx::bytes [%1], [%2], 2048, [%0];\n"
        "@P cp.async.bulk.shared::cluster.global.mbarrier::complete_tx::bytes [%4], [%3], 2048, [%0];\n"
        "}\n" :: "r"(bar), "r"(dst), "l"(xs), "l"(fs), "r"(dst + 2048) : "memory");
}
__device__ __forceinline__ uint32_t bf2_fma(uint32_t a, uint32_t b, uint32_t c) {
    uint32_t d; asm("fma.rn.bf16x2 %0, %1, %2, %3;" : "=r"(d) : "r"(a), "r"(b), "r"(c)); return d;
}
__device__ __forceinline__ float bf_lo(uint32_t v) { return __uint_as_float(v << 16); }
__device__ __forceinline__ float bf_hi(uint32_t v) { return __uint_as_float(v & 0xffff0000u); }
__device__ __forceinline__ uint32_t pack_bf2(float lo, float hi) {
    uint32_t d; asm("cvt.rn.bf16x2.f32 %0, %1, %2;" : "=r"(d) : "f"(hi), "f"(lo)); return d;
}

__device__ __forceinline__ void row_math(const uint4 (&xv)[4], const uint4 (&fv)[4], const uint4 (&gv)[4], const uint4 (&bv)[4],
                                         uint32_t alpha2, uint4 (&o)[4]) {
    uint32_t y[16];
#pragma unroll
    for (int j = 0; j < 4; j++) {
        y[j * 4 + 0] = bf2_fma(alpha2, xv[j].x, fv[j].x);
        y[j * 4 + 1] = bf2_fma(alpha2, xv[j].y, fv[j].y);
        y[j * 4 + 2] = bf2_fma(alpha2, xv[j].z, fv[j].z);
        y[j * 4 + 3] = bf2_fma(alpha2, xv[j].w, fv[j].w);
    }
    const float K = __shfl_sync(0xffffffffu, bf_lo(y[0]), 0);
    float d[32];
    float s0 = 0.f, s1 = 0.f, q0 = 0.f, q1 = 0.f;
#pragma unroll
    for (int i = 0; i < 16; i++) {
        const float a = bf_lo(y[i]) - K, c = bf_hi(y[i]) - K;
        d[2 * i] = a; d[2 * i + 1] = c;
        s0 += a; s1 += c;
        q0 = fmaf(a, a, q0); q1 = fmaf(c, c, q1);
    }
    float s = s0 + s1, q = q0 + q1;
#pragma unroll
    for (int m = 16; m >= 1; m >>= 1) {
        s += __shfl_xor_sync(0xffffffffu, s, m);
        q += __shfl_xor_sync(0xffffffffu, q, m);
    }
    const float mean = s * (1.0f / D);
    const float var  = fmaxf(fmaf(-mean, mean, q * (1.0f / D)), 0.f) + 1e-5f;
    float rstd; asm("rsqrt.approx.ftz.f32 %0, %1;" : "=f"(rstd) : "f"(var));
    const float nb = -mean * rstd;
#pragma unroll
    for (int j = 0; j < 4; j++) {
        o[j].x = bf2_fma(pack_bf2(fmaf(d[8 * j + 0], rstd, nb), fmaf(d[8 * j + 1], rstd, nb)), gv[j].x, bv[j].x);
        o[j].y = bf2_fma(pack_bf2(fmaf(d[8 * j + 2], rstd, nb), fmaf(d[8 * j + 3], rstd, nb)), gv[j].y, bv[j].y);
        o[j].z = bf2_fma(pack_bf2(fmaf(d[8 * j + 4], rstd, nb), fmaf(d[8 * j + 5], rstd, nb)), gv[j].z, bv[j].z);
        o[j].w = bf2_fma(pack_bf2(fmaf(d[8 * j + 6], rstd, nb), fmaf(d[8 * j + 7], rstd, nb)), gv[j].w, bv[j].w);
    }
}

__device__ __forceinline__ void release_parked(uint32_t src, uint4* dst) {
    uint4 t[4];
#pragma unroll
    for (int j = 0; j < 4; j++) t[j] = lds128(src + j * 512);
#pragma unroll
    for (int j = 0; j < 4; j++) stg(dst + j * 32, t[j]);
}

__global__ void __launch_bounds__(NW * 32 + 32, 1)
deepnorm_kernel(const char* __restrict__ x, const char* __restrict__ f, const uint4* __restrict__ g, const uint4* __restrict__ b,
                const void* __restrict__ alpha, uint4* __restrict__ out) {
    extern __shared__ __align__(128) char smem[];
    const uint32_t c0 = clk() - LEAD;
    const int cta = blockIdx.x;
    const uint32_t sb  = smem_u32(smem);
    const uint32_t sm0 = sb + 256;
    const char* xp = x + (size_t)cta * ROW_BYTES;
    const char* fp = f + (size_t)cta * ROW_BYTES;
    asm volatile("{\n.reg .pred P, Q;\nelect.sync _|Q, 0xffffffff;\nsetp.lt.and.u32 P, %5, 32, Q;\n"
        "@P mbarrier.init.shared::cta.b64 [%0], 1;\n"
        "@P fence.mbarrier_init.release.cluster;\n"
        "@P mbarrier.arrive.expect_tx.shared::cta.b64 _, [%0], 4096;\n"
        "@P cp.async.bulk.shared::cluster.global.mbarrier::complete_tx::bytes [%1], [%2], 2048, [%0];\n"
        "@P cp.async.bulk.shared::cluster.global.mbarrier::complete_tx::bytes [%4], [%3], 2048, [%0];\n"
        "}\n" :: "r"(sb), "r"(sm0), "l"(xp), "l"(fp), "r"(sm0 + 2048), "r"(threadIdx.x) : "memory");
    const int wid = __shfl_sync(0xffffffffu, threadIdx.x >> 5, 0);
    if (wid == 0) {
        uint32_t tgt = c0, bar = sb, dst = sm0;
#pragma unroll
        for (int r = 1; r < PB; r++) {
            xp += NCTA * ROW_BYTES; fp += NCTA * ROW_BYTES; bar += 8; dst += 2 * ROW_BYTES;
            tgt += PACE;
            while ((int)(tgt - clk()) > 0) { }
            fetch_row_init(bar, dst, xp, fp);
        }
        asm volatile("bar.sync 1, %0;" :: "n"(NW * 32 + 32) : "memory");
#pragma unroll 1
        for (int r = PB; r < NROWS; r++) {
            xp += NCTA * ROW_BYTES; fp += NCTA * ROW_BYTES; bar += 8; dst += 2 * ROW_BYTES;
            tgt += PACE;
            while ((int)(tgt - clk()) > 0) { }
            fetch_row(bar, dst, xp, fp);
        }
        return;
    }
    const int lane = threadIdx.x & 31;
    const int warp = wid - 1;
    {
        static_assert(NW == 8 && NROWS == 32, "barrier init pattern");
        const uint32_t b0 = sb + warp * 8;
        asm volatile("{\n.reg .pred P, Q;\nelect.sync _|P, 0xffffffff;\nsetp.ge.and.u32 Q, %1, %2, P;\n"
            "@Q mbarrier.init.shared::cta.b64 [%0], 1;\n"
            "@P mbarrier.init.shared::cta.b64 [%0+64], 1;\n"
            "@P mbarrier.init.shared::cta.b64 [%0+128], 1;\n"
            "@P mbarrier.init.shared::cta.b64 [%0+192], 1;\n"
            "@P fence.mbarrier_init.release.cluster;\n}\n" :: "r"(b0), "r"(warp), "n"(PB) : "memory");
    }
    uint4 gv[4], bv[4];
    uint32_t alpha_raw;
    asm volatile("ld.global.nc.u16 %0, [%1];" : "=r"(alpha_raw) : "l"(alpha) : "memory");
#pragma unroll
    for (int j = 0; j < 4; j++) { gv[j] = ldg_nc(g + lane + j * 32); bv[j] = ldg_nc(b + lane + j * 32); }
    asm volatile("bar.sync 1, %0;" :: "n"(NW * 32 + 32) : "memory");
    int r = warp;
#pragma unroll 1
    do {
        const uint32_t src = sm0 + r * (2 * ROW_BYTES) + lane * 16;
        uint4* op = out + (size_t)(cta + r * NCTA) * (ROW_BYTES / 16) + lane;
        const bool last   = r >= NROWS - NW;
        const bool parked = last && (r - NW >= HOLD);
        const int  rel    = REL_PARK + (warp >> 2);
        if (parked && r > rel) {
            mbar_wait(sb + rel * 8);
            release_parked(src - NW * 2 * ROW_BYTES, op - NW * NCTA * (ROW_BYTES / 16));
        }
        mbar_wait(sb + r * 8);
        uint4 xv[4], fv[4], o[4];
#pragma unroll
        for (int j = 0; j < 4; j++) { xv[j] = lds128(src + j * 512); fv[j] = lds128(src + ROW_BYTES + j * 512); }
        uint32_t alpha2; asm volatile("prmt.b32 %0, %1, %1, 0x1010;" : "=r"(alpha2) : "r"(alpha_raw));
        row_math(xv, fv, gv, bv, alpha2, o);
        if (!last && r >= HOLD) {
#pragma unroll
            for (int j = 0; j < 4; j++) sts128(src + j * 512, o[j]);
        } else {
            if (parked && r <= rel) {
                mbar_wait(sb + rel * 8);
                release_parked(src - NW * 2 * ROW_BYTES, op - NW * NCTA * (ROW_BYTES / 16));
            }
            if (last && r < REL_LAST) mbar_wait(sb + REL_LAST * 8);
#pragma unroll
            for (int j = 0; j < 4; j++) stg(op + j * 32, o[j]);
        }
        r += NW;
    } while (r < NROWS);
}

}

extern "C" void kernel_launch(void* const* d_in, const int* in_sizes, int n_in, void* d_out, int out_size) {
    (void)in_sizes; (void)n_in; (void)out_size;
    static bool attr_set = false;
    if (!attr_set) {
        cudaFuncSetAttribute(deepnorm_kernel, cudaFuncAttributeMaxDynamicSharedMemorySize, SMEM_BYTES);
        attr_set = true;
    }
    deepnorm_kernel<<<NCTA, NW * 32 + 32, SMEM_BYTES, cudaStreamPerThread>>>(
        (const char*)d_in[0], (const char*)d_in[1], (const uint4*)d_in[2], (const uint4*)d_in[3],
        d_in[4], (uint4*)d_out);
}
```

```cpp
#include <cuda_runtime.h>
#include <cuda_bf16.h>
#include <stdint.h>

namespace {

constexpr int D         = 1024;
constexpr int ROW_BYTES = D * 2;
constexpr int NCTA      = 128;
constexpr int NROWS     = 32;
constexpr int NW        = 8;
constexpr int PB        = 3;
constexpr int PACE      = 295;
constexpr int LEAD      = 128;
constexpr int HOLD      = 16;
constexpr int REL_PARK  = 27;
constexpr int REL_LAST  = 29;
constexpr int SMEM_BYTES = 256 + NROWS * 2 * ROW_BYTES;

__device__ __forceinline__ uint32_t smem_u32(const void* p) { return (uint32_t)__cvta_generic_to_shared(p); }
__device__ __forceinline__ uint32_t clk() { uint32_t t; asm volatile("mov.u32 %0, %clock;" : "=r"(t) :: "memory"); return t; }
__device__ __forceinline__ uint4 ldg_nc(const void* p) {
    uint4 v; asm volatile("ld.global.nc.v4.u32 {%0,%1,%2,%3}, [%4];" : "=r"(v.x), "=r"(v.y), "=r"(v.z), "=r"(v.w) : "l"(p) : "memory"); return v;
}
__device__ __forceinline__ uint64_t evict_first_policy() {
    uint64_t p; asm volatile("createpolicy.fractional.L2::evict_first.b64 %0, 1.0;" : "=l"(p)); return p;
}
__device__ __forceinline__ void stg(void* p, uint4 v, uint64_t pol) {
    asm volatile("st.global.L2::cache_hint.v4.u32 [%4], {%0,%1,%2,%3}, %5;" :: "r"(v.x), "r"(v.y), "r"(v.z), "r"(v.w), "l"(p), "l"(pol) : "memory");
}
__device__ __forceinline__ uint4 lds128(uint32_t a) {
    uint4 v; asm volatile("ld.shared.v4.u32 {%0,%1,%2,%3}, [%4];" : "=r"(v.x), "=r"(v.y), "=r"(v.z), "=r"(v.w) : "r"(a) : "memory"); return v;
}
__device__ __forceinline__ void sts128(uint32_t a, uint4 v) {
    asm volatile("st.shared.v4.u32 [%4], {%0,%1,%2,%3};" :: "r"(v.x), "r"(v.y), "r"(v.z), "r"(v.w), "r"(a) : "memory");
}
__device__ __forceinline__ void mbar_wait(uint32_t bar) {
    asm volatile("{\n.reg .pred p;\nWAIT_LOOP:\nmbarrier.try_wait.parity.shared::cta.b64 p, [%0], 0;\n@p bra WAIT_DONE;\nbra WAIT_LOOP;\nWAIT_DONE:\n}" :: "r"(bar) : "memory");
}
__device__ __forceinline__ void fetch_row_init(uint32_t bar, uint32_t dst, const void* xs, const void* fs) {
    asm volatile("{\n.reg .pred P;\nelect.sync _|P, 0xffffffff;\n"
        "@P mbarrier.init.shared::cta.b64 [%0], 1;\n"
        "@P fence.mbarrier_init.release.cluster;\n"
        "@P mbarrier.arrive.expect_tx.shared::cta.b64 _, [%0], 4096;\n"
        "@P cp.async.bulk.shared::cluster.global.mbarrier::complete_tx::bytes [%1], [%2], 2048, [%0];\n"
        "@P cp.async.bulk.shared::cluster.global.mbarrier::complete_tx::bytes [%4], [%3], 2048, [%0];\n"
        "}\n" :: "r"(bar), "r"(dst), "l"(xs), "l"(fs), "r"(dst + 2048) : "memory");
}
__device__ __forceinline__ void fetch_row(uint32_t bar, uint32_t dst, const void* xs, const void* fs, uint64_t pol) {
    asm volatile("{\n.reg .pred P;\nelect.sync _|P, 0xffffffff;\n"
        "@P mbarrier.arrive.expect_tx.shared::cta.b64 _, [%0], 4096;\n"
        "@P cp.async.bulk.shared::cluster.global.mbarrier::complete_tx::bytes.L2::cache_hint [%1], [%2], 2048, [%0], %5;\n"
        "@P cp.async.bulk.shared::cluster.global.mbarrier::complete_tx::bytes.L2::cache_hint [%4], [%3], 2048, [%0], %5;\n"
        "}\n" :: "r"(bar), "r"(dst), "l"(xs), "l"(fs), "r"(dst + 2048), "l"(pol) : "memory");
}
__device__ __forceinline__ uint32_t bf2_fma(uint32_t a, uint32_t b, uint32_t c) {
    uint32_t d; asm("fma.rn.bf16x2 %0, %1, %2, %3;" : "=r"(d) : "r"(a), "r"(b), "r"(c)); return d;
}
__device__ __forceinline__ float bf_lo(uint32_t v) { return __uint_as_float(v << 16); }
__device__ __forceinline__ float bf_hi(uint32_t v) { return __uint_as_float(v & 0xffff0000u); }
__device__ __forceinline__ uint32_t pack_bf2(float lo, float hi) {
    uint32_t d; asm("cvt.rn.bf16x2.f32 %0, %1, %2;" : "=r"(d) : "f"(hi), "f"(lo)); return d;
}

__device__ __forceinline__ void row_math(const uint4 (&xv)[4], const uint4 (&fv)[4], const uint4 (&gv)[4], const uint4 (&bv)[4],
                                         uint32_t alpha2, uint4 (&o)[4]) {
    uint32_t y[16];
#pragma unroll
    for (int j = 0; j < 4; j++) {
        y[j * 4 + 0] = bf2_fma(alpha2, xv[j].x, fv[j].x);
        y[j * 4 + 1] = bf2_fma(alpha2, xv[j].y, fv[j].y);
        y[j * 4 + 2] = bf2_fma(alpha2, xv[j].z, fv[j].z);
        y[j * 4 + 3] = bf2_fma(alpha2, xv[j].w, fv[j].w);
    }
    const float K = __shfl_sync(0xffffffffu, bf_lo(y[0]), 0);
    float d[32];
    float s0 = 0.f, s1 = 0.f, q0 = 0.f, q1 = 0.f;
#pragma unroll
    for (int i = 0; i < 16; i++) {
        const float a = bf_lo(y[i]) - K, c = bf_hi(y[i]) - K;
        d[2 * i] = a; d[2 * i + 1] = c;
        s0 += a; s1 += c;
        q0 = fmaf(a, a, q0); q1 = fmaf(c, c, q1);
    }
    float s = s0 + s1, q = q0 + q1;
#pragma unroll
    for (int m = 16; m >= 1; m >>= 1) {
        s += __shfl_xor_sync(0xffffffffu, s, m);
        q += __shfl_xor_sync(0xffffffffu, q, m);
    }
    const float mean = s * (1.0f / D);
    const float var  = fmaxf(fmaf(-mean, mean, q * (1.0f / D)), 0.f) + 1e-5f;
    float rstd; asm("rsqrt.approx.ftz.f32 %0, %1;" : "=f"(rstd) : "f"(var));
    const float nb = -mean * rstd;
#pragma unroll
    for (int j = 0; j < 4; j++) {
        o[j].x = bf2_fma(pack_bf2(fmaf(d[8 * j + 0], rstd, nb), fmaf(d[8 * j + 1], rstd, nb)), gv[j].x, bv[j].x);
        o[j].y = bf2_fma(pack_bf2(fmaf(d[8 * j + 2], rstd, nb), fmaf(d[8 * j + 3], rstd, nb)), gv[j].y, bv[j].y);
        o[j].z = bf2_fma(pack_bf2(fmaf(d[8 * j + 4], rstd, nb), fmaf(d[8 * j + 5], rstd, nb)), gv[j].z, bv[j].z);
        o[j].w = bf2_fma(pack_bf2(fmaf(d[8 * j + 6], rstd, nb), fmaf(d[8 * j + 7], rstd, nb)), gv[j].w, bv[j].w);
    }
}

__device__ __forceinline__ void release_parked(uint32_t src, uint4* dst, uint64_t pol) {
    uint4 t[4];
#pragma unroll
    for (int j = 0; j < 4; j++) t[j] = lds128(src + j * 512);
#pragma unroll
    for (int j = 0; j < 4; j++) stg(dst + j * 32, t[j], pol);
}

__global__ void __launch_bounds__(NW * 32 + 32, 1)
deepnorm_kernel(const char* __restrict__ x, const char* __restrict__ f, const uint4* __restrict__ g, const uint4* __restrict__ b,
                const void* __restrict__ alpha, uint4* __restrict__ out) {
    extern __shared__ __align__(128) char smem[];
    const uint32_t c0 = clk() - LEAD;
    const int cta = blockIdx.x;
    const uint32_t sb  = smem_u32(smem);
    const uint32_t sm0 = sb + 256;
    const char* xp = x + (size_t)cta * ROW_BYTES;
    const char* fp = f + (size_t)cta * ROW_BYTES;
    asm volatile("{\n.reg .pred P, Q;\nelect.sync _|Q, 0xffffffff;\nsetp.lt.and.u32 P, %5, 32, Q;\n"
        "@P mbarrier.init.shared::cta.b64 [%0], 1;\n"
        "@P fence.mbarrier_init.release.cluster;\n"
        "@P mbarrier.arrive.expect_tx.shared::cta.b64 _, [%0], 4096;\n"
        "@P cp.async.bulk.shared::cluster.global.mbarrier::complete_tx::bytes [%1], [%2], 2048, [%0];\n"
        "@P cp.async.bulk.shared::cluster.global.mbarrier::complete_tx::bytes [%4], [%3], 2048, [%0];\n"
        "}\n" :: "r"(sb), "r"(sm0), "l"(xp), "l"(fp), "r"(sm0 + 2048), "r"(threadIdx.x) : "memory");
    const int wid = __shfl_sync(0xffffffffu, threadIdx.x >> 5, 0);
    if (wid == 0) {
        uint32_t tgt = c0, bar = sb, dst = sm0;
#pragma unroll
        for (int r = 1; r < PB; r++) {
            xp += NCTA * ROW_BYTES; fp += NCTA * ROW_BYTES; bar += 8; dst += 2 * ROW_BYTES;
            tgt += PACE;
            while ((int)(tgt - clk()) > 0) { }
            fetch_row_init(bar, dst, xp, fp);
        }
        asm volatile("bar.sync 1, %0;" :: "n"(NW * 32 + 32) : "memory");
        const uint64_t pol = evict_first_policy();
#pragma unroll 1
        for (int r = PB; r < NROWS; r++) {
            xp += NCTA * ROW_BYTES; fp += NCTA * ROW_BYTES; bar += 8; dst += 2 * ROW_BYTES;
            tgt += PACE;
            while ((int)(tgt - clk()) > 0) { }
            fetch_row(bar, dst, xp, fp, pol);
        }
        return;
    }
    const int lane = threadIdx.x & 31;
    const int warp = wid - 1;
    {
        static_assert(NW == 8 && NROWS == 32, "barrier init pattern");
        const uint32_t b0 = sb + warp * 8;
        asm volatile("{\n.reg .pred P, Q;\nelect.sync _|P, 0xffffffff;\nsetp.ge.and.u32 Q, %1, %2, P;\n"
            "@Q mbarrier.init.shared::cta.b64 [%0], 1;\n"
            "@P mbarrier.init.shared::cta.b64 [%0+64], 1;\n"
            "@P mbarrier.init.shared::cta.b64 [%0+128], 1;\n"
            "@P mbarrier.init.shared::cta.b64 [%0+192], 1;\n"
            "@P fence.mbarrier_init.release.cluster;\n}\n" :: "r"(b0), "r"(warp), "n"(PB) : "memory");
    }
    uint4 gv[4], bv[4];
    uint32_t alpha_raw;
    asm volatile("ld.global.nc.u16 %0, [%1];" : "=r"(alpha_raw) : "l"(alpha) : "memory");
#pragma unroll
    for (int j = 0; j < 4; j++) { gv[j] = ldg_nc(g + lane + j * 32); bv[j] = ldg_nc(b + lane + j * 32); }
    const uint64_t pol = evict_first_policy();
    asm volatile("bar.sync 1, %0;" :: "n"(NW * 32 + 32) : "memory");
    int r = warp;
#pragma unroll 1
    do {
        const uint32_t src = sm0 + r * (2 * ROW_BYTES) + lane * 16;
        uint4* op = out + (size_t)(cta + r * NCTA) * (ROW_BYTES / 16) + lane;
        const bool last   = r >= NROWS - NW;
        const bool parked = last && (r - NW >= HOLD);
        const int  rel    = REL_PARK + (warp >> 2);
        if (parked && r > rel) {
            mbar_wait(sb + rel * 8);
            release_parked(src - NW * 2 * ROW_BYTES, op - NW * NCTA * (ROW_BYTES / 16), pol);
        }
        mbar_wait(sb + r * 8);
        uint4 xv[4], fv[4], o[4];
#pragma unroll
        for (int j = 0; j < 4; j++) { xv[j] = lds128(src + j * 512); fv[j] = lds128(src + ROW_BYTES + j * 512); }
        uint32_t alpha2; asm volatile("prmt.b32 %0, %1, %1, 0x1010;" : "=r"(alpha2) : "r"(alpha_raw));
        row_math(xv, fv, gv, bv, alpha2, o);
        if (!last && r >= HOLD) {
#pragma unroll
            for (int j = 0; j < 4; j++) sts128(src + j * 512, o[j]);
        } else {
            if (parked && r <= rel) {
                mbar_wait(sb + rel * 8);
                release_parked(src - NW * 2 * ROW_BYTES, op - NW * NCTA * (ROW_BYTES / 16), pol);
            }
            if (last && r < REL_LAST) mbar_wait(sb + REL_LAST * 8);
#pragma unroll
            for (int j = 0; j < 4; j++) stg(op + j * 32, o[j], pol);
        }
        r += NW;
    } while (r < NROWS);
}

}

extern "C" void kernel_launch(void* const* d_in, const int* in_sizes, int n_in, void* d_out, int out_size) {
    (void)in_sizes; (void)n_in; (void)out_size;
    static bool attr_set = false;
    if (!attr_set) {
        cudaFuncSetAttribute(deepnorm_kernel, cudaFuncAttributeMaxDynamicSharedMemorySize, SMEM_BYTES);
        attr_set = true;
    }
    deepnorm_kernel<<<NCTA, NW * 32 + 32, SMEM_BYTES, cudaStreamPerThread>>>(
        (const char*)d_in[0], (const char*)d_in[1], (const uint4*)d_in[2], (const uint4*)d_in[3],
        d_in[4], (uint4*)d_out);
}
```
